```python
import torch

def _softmax(x, axis=-1):
    return torch.softmax(x, dim=axis)
def _gelu(x):
    return torch.nn.functional.gelu(x, approximate="tanh")
def _silu(x):
    return torch.nn.functional.silu(x)
def _sigmoid(x):
    return torch.sigmoid(x)
def _layernorm(x, axis=-1, eps=1e-5):
    m = x.mean(dim=axis, keepdim=True)
    v = x.var(dim=axis, keepdim=True, unbiased=False)
    return (x - m) / torch.sqrt(v + eps)
def _scatter_add(tgt, idx, src, axis=0):
    return tgt.clone().index_add_(axis, idx, src)
def _segment_sum(src, seg, n):
    out = torch.zeros((n,) + src.shape[1:], dtype=src.dtype)
    return out.index_add_(0, seg, src)
def _pad(x, pw):
    flat = tuple(v for pair in reversed(pw) for v in pair)
    return torch.nn.functional.pad(x, flat)

kernel_name = 'standalone__low_rank_proj_linformer__decode'

def setup_inputs():

    _w = (lambda a: (lambda t: t.to(torch.bfloat16) if t.is_floating_point() else t)(torch.as_tensor(a)))
    B, H, Sq, Skv, Dh, R = 4, 16, 1, 8192, 256, 64
    return {
        "q": _w((lambda *s: torch.randn(*s, dtype=torch.bfloat16) * 0.8)(B, H, Sq, Dh)),
        "k": _w((lambda *s: torch.randn(*s, dtype=torch.bfloat16) * 0.8)(B, H, Skv, Dh)),
        "v": _w((lambda *s: torch.randn(*s, dtype=torch.bfloat16) * 0.05)(B, H, Skv, Dh)),
        "e_proj": _w((lambda *s: torch.randn(*s, dtype=torch.bfloat16) * 0.8)(R, Skv) * (Skv ** -0.5)),
        "f_proj": _w((lambda *s: torch.randn(*s, dtype=torch.bfloat16) * 0.05)(R, Skv) * (Skv ** -0.5)),
    }

def reference(q, k, v, e_proj, f_proj):
    B, H, Sq, Dh = q.shape
    kp = torch.einsum("rn,bhnd->bhrd", e_proj, k)
    vp = torch.einsum("rn,bhnd->bhrd", f_proj, v)
    scores = torch.einsum("bhqd,bhrd->bhqr", q, kp) * (Dh ** -0.5)
    p = _softmax(scores, axis=-1)
    o = torch.einsum("bhqr,bhrd->bhqd", p, vp)
    return o
```

```cpp
#include <cuda_runtime.h>
#include <cuda_bf16.h>
#include <cuda.h>
#include <stdint.h>
constexpr int BH=64, NN=8192, DD=256, RR=64;
namespace pr {
__device__ __forceinline__ long long gt(){ long long t; asm volatile("mov.u64 %0, %globaltimer;":"=l"(t)); return t; }
__device__ __forceinline__ void tl_store(bool c, long long* p){ asm volatile("{\n.reg .pred q;\n.reg .u64 t;\nsetp.ne.u32 q, %0, 0;\nmov.u64 t, %globaltimer;\n@q st.global.u64 [%1], t;\n}"::"r"((unsigned)c),"l"(p):"memory"); }
__device__ __forceinline__ uint32_t smem_u32(const void* p){ return (uint32_t)__cvta_generic_to_shared(p); }
__device__ __forceinline__ float bf_lo(uint32_t x){ return __uint_as_float(x<<16); }
__device__ __forceinline__ float bf_hi(uint32_t x){ return __uint_as_float(x&0xffff0000u); }
__device__ __forceinline__ void mbar_init(uint32_t bar, uint32_t cnt){ asm volatile("mbarrier.init.shared::cta.b64 [%0], %1;"::"r"(bar),"r"(cnt):"memory"); }
__device__ __forceinline__ void mbar_expect_tx(uint32_t bar, uint32_t bytes){ asm volatile("mbarrier.arrive.expect_tx.shared::cta.b64 _, [%0], %1;"::"r"(bar),"r"(bytes):"memory"); }
__device__ __forceinline__ void mbar_arrive(uint32_t bar){ asm volatile("mbarrier.arrive.shared::cta.b64 _, [%0];"::"r"(bar):"memory"); }
__device__ __forceinline__ bool mbar_try(uint32_t bar, uint32_t parity){ uint32_t ok; asm volatile("{\n.reg .pred p;\nmbarrier.try_wait.parity.shared::cta.b64 p, [%1], %2;\nselp.u32 %0,1,0,p;\n}":"=r"(ok):"r"(bar),"r"(parity):"memory"); return ok; }
__device__ __forceinline__ void mbar_wait(uint32_t bar, uint32_t parity){ if(mbar_try(bar,parity)) return; long long t0=clock64(); while(!mbar_try(bar,parity)){ if(clock64()-t0>200000000ll) __trap(); } }
__device__ __forceinline__ void bulk_load(uint32_t dst, const void* src, uint32_t bytes, uint32_t bar){
  asm volatile("cp.async.bulk.shared::cluster.global.mbarrier::complete_tx::bytes [%0], [%1], %2, [%3];"::"r"(dst),"l"(src),"r"(bytes),"r"(bar):"memory"); }
__device__ __forceinline__ void bulk_load_hint(uint32_t dst, const void* src, uint32_t bytes, uint32_t bar, uint64_t pol){
  asm volatile("cp.async.bulk.shared::cluster.global.mbarrier::complete_tx::bytes.L2::cache_hint [%0], [%1], %2, [%3], %4;"::"r"(dst),"l"(src),"r"(bytes),"r"(bar),"l"(pol):"memory"); }
__device__ __forceinline__ void tma2d(uint32_t dst, const CUtensorMap* tm, int c0, int c1, uint32_t bar){
  asm volatile("cp.async.bulk.tensor.2d.shared::cluster.global.mbarrier::complete_tx::bytes [%0], [%1, {%3, %4}], [%2];"::"r"(dst),"l"(tm),"r"(bar),"r"(c0),"r"(c1):"memory"); }
__device__ __forceinline__ void tma2d_hint(uint32_t dst, const CUtensorMap* tm, int c0, int c1, uint32_t bar, uint64_t pol){
  asm volatile("cp.async.bulk.tensor.2d.shared::cluster.global.mbarrier::complete_tx::bytes.L2::cache_hint [%0], [%1, {%3, %4}], [%2], %5;"::"r"(dst),"l"(tm),"r"(bar),"r"(c0),"r"(c1),"l"(pol):"memory"); }
__device__ __forceinline__ uint4 lds128(uint32_t a){ uint4 v; asm volatile("ld.shared.v4.u32 {%0,%1,%2,%3}, [%4];":"=r"(v.x),"=r"(v.y),"=r"(v.z),"=r"(v.w):"r"(a)); return v; }
__device__ __forceinline__ float4 lds128f(uint32_t a){ float4 v; asm volatile("ld.shared.v4.f32 {%0,%1,%2,%3}, [%4];":"=f"(v.x),"=f"(v.y),"=f"(v.z),"=f"(v.w):"r"(a)); return v; }
__device__ __forceinline__ float lds32f(uint32_t a){ float v; asm volatile("ld.shared.f32 %0, [%1];":"=f"(v):"r"(a)); return v; }
__device__ __forceinline__ unsigned lds32(uint32_t a){ unsigned v; asm volatile("ld.shared.u32 %0, [%1];":"=r"(v):"r"(a)); return v; }
__device__ __forceinline__ void ldsm4(uint32_t a, uint32_t& r0,uint32_t& r1,uint32_t& r2,uint32_t& r3){ asm volatile("ldmatrix.sync.aligned.m8n8.x4.shared.b16 {%0,%1,%2,%3}, [%4];":"=r"(r0),"=r"(r1),"=r"(r2),"=r"(r3):"r"(a)); }
__device__ __forceinline__ void ldsm4t(uint32_t a, uint32_t& r0,uint32_t& r1,uint32_t& r2,uint32_t& r3){ asm volatile("ldmatrix.sync.aligned.m8n8.x4.trans.shared.b16 {%0,%1,%2,%3}, [%4];":"=r"(r0),"=r"(r1),"=r"(r2),"=r"(r3):"r"(a)); }
__device__ __forceinline__ void mma(float (&c)[4], uint32_t a0,uint32_t a1,uint32_t a2,uint32_t a3,uint32_t b0,uint32_t b1){
  asm volatile("mma.sync.aligned.m16n8k16.row.col.f32.bf16.bf16.f32 {%0,%1,%2,%3}, {%4,%5,%6,%7}, {%8,%9}, {%0,%1,%2,%3};":"+f"(c[0]),"+f"(c[1]),"+f"(c[2]),"+f"(c[3]):"r"(a0),"r"(a1),"r"(a2),"r"(a3),"r"(b0),"r"(b1)); }
__device__ __forceinline__ void bar_sync(int id, int n){ __syncwarp(); asm volatile("bar.sync %0, %1;"::"r"(id),"r"(n):"memory"); }
__device__ __forceinline__ void bar_arrive(int id, int n){ __syncwarp(); asm volatile("bar.arrive %0, %1;"::"r"(id),"r"(n):"memory"); }
__device__ __forceinline__ void red_add(float* p, float v){ asm volatile("red.relaxed.gpu.global.add.f32 [%0], %1;"::"l"(p),"f"(v):"memory"); }
__device__ __forceinline__ void red_add2(float* p, float a, float b){ asm volatile("red.relaxed.gpu.global.add.v2.f32 [%0], {%1,%2};"::"l"(p),"f"(a),"f"(b):"memory"); }
__device__ __forceinline__ float atom_add(float* p, float v){ float r; asm volatile("atom.relaxed.gpu.global.add.f32 %0, [%1], %2;":"=f"(r):"l"(p),"f"(v):"memory"); return r; }
__device__ __forceinline__ void atom_add2(float& r0, float& r1, float* p, float a, float b){ asm volatile("atom.relaxed.gpu.global.add.v2.f32 {%0,%1}, [%2], {%3,%4};":"=f"(r0),"=f"(r1):"l"(p),"f"(a),"f"(b):"memory"); }
__device__ __forceinline__ float4 atom_read4(float* p){ float4 r; asm volatile("atom.relaxed.gpu.global.add.v4.f32 {%0,%1,%2,%3}, [%4], {%5,%5,%5,%5};":"=f"(r.x),"=f"(r.y),"=f"(r.z),"=f"(r.w):"l"(p),"f"(0.f):"memory"); return r; }
__device__ __forceinline__ void red_inc_relaxed(unsigned* p){ asm volatile("red.relaxed.gpu.global.add.u32 [%0], 1;"::"l"(p):"memory"); }
__device__ __forceinline__ unsigned atom_inc_relaxed(unsigned* p){ unsigned v; asm volatile("atom.relaxed.gpu.global.add.u32 %0, [%1], 1;":"=r"(v):"l"(p):"memory"); return v; }
__device__ __forceinline__ unsigned atoms_inc(uint32_t a){ unsigned v; asm volatile("atom.relaxed.cta.shared.add.u32 %0, [%1], 1;":"=r"(v):"r"(a):"memory"); return v; }
__device__ __forceinline__ unsigned ld_acquire(const unsigned* p){ unsigned v; asm volatile("ld.acquire.gpu.global.u32 %0, [%1];":"=r"(v):"l"(p):"memory"); return v; }
__device__ __forceinline__ unsigned ld_relaxed(const unsigned* p){ unsigned v; asm volatile("ld.relaxed.gpu.global.u32 %0, [%1];":"=r"(v):"l"(p):"memory"); return v; }
__device__ __forceinline__ float ld_relaxed_f(const float* p){ float v; asm volatile("ld.relaxed.gpu.global.f32 %0, [%1];":"=f"(v):"l"(p):"memory"); return v; }
__device__ __forceinline__ float4 ld_relaxed_f4(const float* p){ float4 v; asm volatile("ld.relaxed.gpu.global.v4.f32 {%0,%1,%2,%3}, [%4];":"=f"(v.x),"=f"(v.y),"=f"(v.z),"=f"(v.w):"l"(p):"memory"); return v; }
__device__ __forceinline__ void fence_gpu(){ asm volatile("fence.acq_rel.gpu;":::"memory"); }
__device__ __forceinline__ unsigned lds_acquire(uint32_t a){ unsigned v; asm volatile("ld.acquire.cta.shared.u32 %0, [%1];":"=r"(v):"r"(a):"memory"); return v; }
__device__ __forceinline__ unsigned lds_volatile(uint32_t a){ unsigned v; asm volatile("ld.volatile.shared.u32 %0, [%1];":"=r"(v):"r"(a):"memory"); return v; }
__device__ __forceinline__ void sts_release(uint32_t a, unsigned v){ asm volatile("st.release.cta.shared.u32 [%0], %1;"::"r"(a),"r"(v):"memory"); }
__device__ __forceinline__ void sts32(uint32_t a, unsigned v){ asm volatile("st.volatile.shared.u32 [%0], %1;"::"r"(a),"r"(v):"memory"); }
__device__ __forceinline__ void sts16(uint32_t a, uint16_t v){ asm volatile("st.shared.u16 [%0], %1;"::"r"(a),"h"(v):"memory"); }
__device__ __forceinline__ void sts64f(uint32_t a, float x, float y){ asm volatile("st.shared.v2.f32 [%0], {%1,%2};"::"r"(a),"f"(x),"f"(y):"memory"); }
__device__ __forceinline__ void sts128f(uint32_t a, float4 v){ asm volatile("st.shared.v4.f32 [%0], {%1,%2,%3,%4};"::"r"(a),"f"(v.x),"f"(v.y),"f"(v.z),"f"(v.w):"memory"); }
__device__ __forceinline__ uint16_t bf16_bits(float x){ return __bfloat16_as_ushort(__float2bfloat16_rn(x)); }
__device__ __forceinline__ void consume(float x){ asm volatile("{\n.reg .f32 t;\nmov.f32 t, %0;\n}"::"f"(x):"memory"); }

}
namespace v25 {
using namespace pr;
__device__ long long g_tl[20000*4+1024];
constexpr int T=64, CH=NN/T;
constexpr int NK=BH*CH;
constexpr int STAGE_BYTES=49*1024;
constexpr int OFF_SLICE=32768, OFF_Q=49152;
struct Scratch {
  float spart[BH*CH*RR];
  float opart[BH*CH*DD];
  float p[BH*RR];
  unsigned ticket[2][32];
  unsigned done[32];
};
template<int ID> __device__ __align__(1024) Scratch g_scr;
enum { IT_END=-1 };
__device__ __forceinline__ void prefetch_l2(const void* p, uint32_t bytes){ asm volatile("cp.async.bulk.prefetch.L2.global [%0], %1;"::"l"(p),"r"(bytes):"memory"); }
__device__ __forceinline__ float tagged(float x, unsigned tag){ return __uint_as_float((__float_as_uint(x)&~1u)|tag); }
__device__ __forceinline__ bool ok4(const float4& v, unsigned tag){ return (((__float_as_uint(v.x)^tag)|(__float_as_uint(v.y)^tag)|(__float_as_uint(v.z)^tag)|(__float_as_uint(v.w)^tag))&1u)==0; }
__device__ __forceinline__ void st_relaxed_f(float* p, float v){ asm volatile("st.relaxed.gpu.global.f32 [%0], %1;"::"l"(p),"f"(v):"memory"); }
__device__ __forceinline__ void st_relaxed_f2(float* p, float a, float b){ asm volatile("st.relaxed.gpu.global.v2.f32 [%0], {%1,%2};"::"l"(p),"f"(a),"f"(b):"memory"); }
__device__ __forceinline__ void st_relaxed_f4(float* p, float4 v){ asm volatile("st.relaxed.gpu.global.v4.f32 [%0], {%1,%2,%3,%4};"::"l"(p),"f"(v.x),"f"(v.y),"f"(v.z),"f"(v.w):"memory"); }
__device__ __forceinline__ void wait_prog(uint32_t a, int thr){
  int spins=0;
  while((int)lds_volatile(a)<thr-1500){ __nanosleep(1000); if(++spins>(1<<20)) __trap(); }
  while((int)lds_volatile(a)<thr){ __nanosleep(100); if(++spins>(1<<22)) __trap(); }
}
template<int NLD,int STRIDE> __device__ __forceinline__ void gather(float4& acc, const float* base, int n, unsigned tag, int sleep_ns){
  int spins=0; unsigned pend=(1u<<n)-1u;
  float4 v[NLD];
  #pragma unroll
  for(int i=0;i<NLD;i++) v[i]=make_float4(0,0,0,0);
  while(true){
    #pragma unroll
    for(int i=0;i<NLD;i++)
      asm volatile("{\n.reg .pred p;\nsetp.ne.u32 p, %5, 0;\n@p ld.relaxed.gpu.global.v4.f32 {%0,%1,%2,%3}, [%4];\n}":"+f"(v[i].x),"+f"(v[i].y),"+f"(v[i].z),"+f"(v[i].w):"l"(base+i*STRIDE),"r"(pend&(1u<<i)):"memory");
    unsigned bad=0;
    #pragma unroll
    for(int i=0;i<NLD;i++) bad|= ok4(v[i],tag)? 0u : (1u<<i);
    pend&=__reduce_or_sync(~0u,bad);
    if(!pend) break;
    __nanosleep(sleep_ns); if(++spins>(1<<21)) __trap();
  }
  #pragma unroll
  for(int i=0;i<NLD;i++){ acc.x+=v[i].x; acc.y+=v[i].y; acc.z+=v[i].z; acc.w+=v[i].w; }
}
__device__ __forceinline__ void wslice(uint32_t fa, const uint4& p0, const uint4& p1, uint32_t dst, int lane){
  float d0[4]={0,0,0,0}, d1[4]={0,0,0,0};
  uint32_t m0,m1,m2,m3;
  ldsm4t(fa+0*2048,m0,m1,m2,m3); mma(d0,p0.x,0,p0.y,0,m0,m1); mma(d1,p0.x,0,p0.y,0,m2,m3);
  ldsm4t(fa+1*2048,m0,m1,m2,m3); mma(d0,p0.z,0,p0.w,0,m0,m1); mma(d1,p0.z,0,p0.w,0,m2,m3);
  ldsm4t(fa+2*2048,m0,m1,m2,m3); mma(d0,p1.x,0,p1.y,0,m0,m1); mma(d1,p1.x,0,p1.y,0,m2,m3);
  ldsm4t(fa+3*2048,m0,m1,m2,m3); mma(d0,p1.z,0,p1.w,0,m0,m1); mma(d1,p1.z,0,p1.w,0,m2,m3);
  d0[0]+=__shfl_down_sync(~0u,d0[0],4); d0[1]+=__shfl_down_sync(~0u,d0[1],4);
  d1[0]+=__shfl_down_sync(~0u,d1[0],4); d1[1]+=__shfl_down_sync(~0u,d1[1],4);
  if(lane<4){ sts64f(dst+lane*8,d0[0],d0[1]); sts64f(dst+32+lane*8,d1[0],d1[1]); }
}
template<int ROWS,int PITCH> __device__ __forceinline__ void vrows(float (&acc)[8], uint32_t va, uint32_t wa){
  #pragma unroll
  for(int i4=0;i4<ROWS/4;i4++){
    const float4 w4=lds128f(wa+i4*16);
    const float wv[4]={w4.x,w4.y,w4.z,w4.w};
    #pragma unroll
    for(int i=0;i<4;i++){
      const uint4 x=lds128(va+(i4*4+i)*PITCH);
      acc[0]=fmaf(wv[i],bf_lo(x.x),acc[0]); acc[1]=fmaf(wv[i],bf_hi(x.x),acc[1]);
      acc[2]=fmaf(wv[i],bf_lo(x.y),acc[2]); acc[3]=fmaf(wv[i],bf_hi(x.y),acc[3]);
      acc[4]=fmaf(wv[i],bf_lo(x.z),acc[4]); acc[5]=fmaf(wv[i],bf_hi(x.z),acc[5]);
      acc[6]=fmaf(wv[i],bf_lo(x.w),acc[6]); acc[7]=fmaf(wv[i],bf_hi(x.w),acc[7]);
    }
  }
}
__device__ __forceinline__ void fold(float (&acc)[8], int lane){
  { const bool hi=lane&16;
    #pragma unroll
    for(int i=0;i<4;i++){ float snd=hi?acc[i]:acc[i+4], kp=hi?acc[i+4]:acc[i]; acc[i]=kp+__shfl_xor_sync(~0u,snd,16);} }
  { const bool hi=lane&8;
    #pragma unroll
    for(int i=0;i<2;i++){ float snd=hi?acc[i]:acc[i+2], kp=hi?acc[i+2]:acc[i]; acc[i]=kp+__shfl_xor_sync(~0u,snd,8);} }
}

template<int ID, int BOFF, int NCS, int LOFF, int SPARE, int TLI, int ABL>
__global__ void __launch_bounds__(640, 1) kern(const __grid_constant__ CUtensorMap tmE, const __grid_constant__ CUtensorMap tmF, const __grid_constant__ CUtensorMap tmV,
      const char* __restrict__ q, const char* __restrict__ K, const char* __restrict__ V, const char* __restrict__ F, __nv_bfloat16* __restrict__ out){
  constexpr int NS=3;
  constexpr int XROWS=NCS*128;
  constexpr int CHV=(NN-XROWS)/T;
  constexpr int NITEMS=NK+BH*CHV;
  constexpr int NSTAT=2*NS;
  constexpr int NRED=2*NCS+4;
  Scratch* const sc=&g_scr<ID>;
  extern __shared__ __align__(1024) char smem_raw[];
  const uint32_t sbase=(smem_u32(smem_raw)+1023u)&~1023u;
  const uint32_t s_p=sbase+(NS+SPARE)*STAGE_BYTES;
  const uint32_t s_tw=s_p+BH*256;
  const uint32_t s_red=s_tw+NS*512;
  const uint32_t s_full=s_red+NRED*512;
  const uint32_t s_side=s_full+NS*8;
  const uint32_t s_empty=s_side+NS*8;
  const uint32_t s_cbar=s_empty+NS*8;
  const uint32_t s_item=s_cbar+3*4*8;
  const uint32_t s_pready=s_item+NS*4;
  const uint32_t s_par=s_pready+4;
  const uint32_t s_prog=s_par+4;
  const uint32_t s_cs=s_prog+4;
  const int tid=threadIdx.x, warp=tid>>5, lane=tid&31;
  const int grp=warp>>2, wg=warp&3;
  const int nCTA=gridDim.x, cta=blockIdx.x;
  const bool owner= cta<2*BH;
  const int obh=cta>>1, ohalf=cta&1;
  auto vtile=[&](int item){ const int j=item-NK; const int bh=j/CHV; return bh*CH+(j-bh*CHV); };
  if(TLI) tl_store(tid==0, &g_tl[20000*4+256+cta]);

  if(warp>=16 && warp<16+NS){
    const int st=warp-16;
    const uint32_t stage=sbase+st*STAGE_BYTES, bfull=s_full+st*8, bside=s_side+st*8, bempty=s_empty+st*8;
    uint64_t pol; asm volatile("createpolicy.fractional.L2::evict_first.b64 %0, 1.0;":"=l"(pol));
    auto put=[&](int item){
      const bool isV=item>=NK; const int tile= isV? vtile(item):item;
      if(TLI==1) tl_store(true, &g_tl[item*4+0]);
      mbar_expect_tx(bfull, 32768); bulk_load_hint(stage,(isV?V:K)+(size_t)tile*32768,32768,bfull,pol);
      mbar_expect_tx(bside, isV? 8192:8192+512);
      tma2d(stage+OFF_SLICE, isV?&tmF:&tmE, (tile&(CH-1))*T, 0, bside);
      if(!isV) bulk_load(stage+OFF_Q, q+(tile/CH)*512, 512, bside);
    };
    auto putc=[&](int k, uint32_t buf){
      const int n0=NN-XROWS+k*128; const uint32_t cb=s_cbar+k*24;
      if(TLI==1) tl_store(true, &g_tl[(NITEMS+cta*NCS+k)*4+0]);
      mbar_expect_tx(cb, 16384);
      tma2d(buf+OFF_SLICE, &tmF, n0, 0, cb);
      tma2d(buf+OFF_SLICE+8192, &tmF, n0+64, 0, cb);
      mbar_expect_tx(cb+8, 16384);  tma2d_hint(buf, &tmV, ohalf*128, obh*NN+n0, cb+8, pol);
      mbar_expect_tx(cb+16, 16384); tma2d_hint(buf+16384, &tmV, ohalf*128, obh*NN+n0+64, cb+16, pol);
    };
    if(lane==0){
      mbar_init(bfull,1); mbar_init(bside,1); mbar_init(bempty,1);
      asm volatile("fence.mbarrier_init.release.cluster;":::"memory");
      sts32(s_item+st*4, st*nCTA+cta);
    }
    if(st>0) bar_sync(8+st,64);
    if(lane==0) put(st*nCTA+cta);
    if(st+1<NS) bar_arrive(9+st,64);
    __syncthreads();
    if(lane==0){
      unsigned* ticket=&sc->ticket[lds32(s_par)][0];
      int item=(NS+st)*nCTA+cta; uint32_t ph=0;
      while(true){
        mbar_wait(bempty,ph); sts32(s_item+st*4,item); put(item); ph^=1;
        mbar_wait(bfull,ph);
        item=NSTAT*nCTA+(int)atom_inc_relaxed(ticket);
        sts32(s_prog,item);
        if(item>=NITEMS) break;
      }
      int msg=IT_END;
      if(owner){
        const int f=(int)atoms_inc(s_cs);
        if(SPARE && f==0 && NCS>0) putc(0, sbase+NS*STAGE_BYTES);
        const int k=f+SPARE;
        mbar_wait(bempty,ph);
        if(k<NCS){ putc(k,stage); msg=-2-k; }
        else if(SPARE && k==(NCS>1?NCS:1) && NCS>0) msg=-2;
      } else mbar_wait(bempty,ph);
      sts32(s_item+st*4,msg); mbar_arrive(bside);
    }
  } else if(warp==16+NS){
    if(lane==0){ unsigned d=atom_inc_relaxed(&sc->done[0]); sts32(s_par,((d/nCTA)&1u)^1u); sts32(s_pready,0); sts32(s_prog,0); sts32(s_cs,0); }
    if(lane==1) asm volatile("prefetch.tensormap [%0];"::"l"(&tmE):"memory");
    if(lane==2){
      #pragma unroll
      for(int i=0;i<3*NCS;i++) mbar_init(s_cbar+i*8,1);
      asm volatile("fence.mbarrier_init.release.cluster;":::"memory");
    }
    __syncthreads();
    const unsigned tag=lds32(s_par);
    if(cta==0 && lane==0) sc->ticket[tag^1][0]=0;
    wait_prog(s_prog,NK-3000);
    if(lane==0){
      asm volatile("prefetch.tensormap [%0];"::"l"(&tmF):"memory");
      asm volatile("prefetch.tensormap [%0];"::"l"(&tmV):"memory");
      if(cta<128) prefetch_l2(F+cta*8192,8192);
    }
    __syncwarp();
    wait_prog(s_prog,NK-1536);
    const int pos=((lane>>1)&3)*16 + (lane>>4)*4 + ((lane>>3)&1)*2 + (lane&1);
    for(int b0=0;b0<BH && !(ABL&16);b0+=8){
      float v0[8], v1[8]; int done=0, spins=0;
      wait_prog(s_prog,(b0+8)*CH+BOFF+300);
      while(true){
        #pragma unroll
        for(int i=0;i<8;i++) if(i>=done){ v0[i]=ld_relaxed_f(&sc->p[(b0+i)*RR+lane]); v1[i]=ld_relaxed_f(&sc->p[(b0+i)*RR+32+lane]); }
        #pragma unroll
        for(int i=0;i<8;i++) if(i==done && __all_sync(~0u,(((__float_as_uint(v0[i])^tag)|(__float_as_uint(v1[i])^tag))&1u)==0)){
          const uint32_t pb=s_p+(b0+i)*256;
          const uint16_t h0=bf16_bits(v0[i]), h1=bf16_bits(v1[i]);
          sts16(pb+pos*2,h0); sts16(pb+(pos+8)*2,h1);
          sts16(pb+128+pos*2,bf16_bits(v0[i]-bf_lo(h0))); sts16(pb+128+(pos+8)*2,bf16_bits(v1[i]-bf_lo(h1)));
          done++;
        }
        __syncwarp();
        if(lane==0) sts_release(s_pready,b0+done);
        if(done==8) break;
        __nanosleep(1000); if(++spins>(1<<20)) __trap();
      }
    }
  } else if(grp==NS){
    __syncthreads();
    if(owner){
      const unsigned tag=lds32(s_par);
      float4 oa=make_float4(0,0,0,0);
      if(!(ABL&16)){
        if(ohalf==0){
          wait_prog(s_prog,(obh+1)*CH+BOFF);
          float4 a=make_float4(0,0,0,0);
          gather<16,128>(a,&sc->spart[((size_t)obh*CH+wg*32)*RR+lane*4],16,tag,500);
          sts128f(s_red+wg*512+lane*16,a);
          bar_sync(4,128);
          if(wg==0){
            a=lds128f(s_red+(lane&15)*16);
            #pragma unroll
            for(int i=1;i<8;i++){ const float4 b=lds128f(s_red+i*256+(lane&15)*16); a.x+=b.x; a.y+=b.y; a.z+=b.z; a.w+=b.w; }
            a.x*=0.0625f; a.y*=0.0625f; a.z*=0.0625f; a.w*=0.0625f;
            float mx=fmaxf(fmaxf(a.x,a.y),fmaxf(a.z,a.w));
            #pragma unroll
            for(int o=8;o;o>>=1) mx=fmaxf(mx,__shfl_xor_sync(~0u,mx,o));
            a.x=__expf(a.x-mx); a.y=__expf(a.y-mx); a.z=__expf(a.z-mx); a.w=__expf(a.w-mx);
            float z=(a.x+a.y)+(a.z+a.w);
            #pragma unroll
            for(int o=8;o;o>>=1) z+=__shfl_xor_sync(~0u,z,o);
            const float iz=1.0f/z;
            if(lane<16) st_relaxed_f4(&sc->p[obh*RR+lane*4], make_float4(tagged(a.x*iz,tag),tagged(a.y*iz,tag),tagged(a.z*iz,tag),tagged(a.w*iz,tag)));
          }
        }
        const float* base=&sc->opart[((size_t)obh*CH+wg)*DD+ohalf*128+lane*4];
        long long tx=0;
        for(int b=0;b<2;b++){
          const int rdy=NK+obh*CHV+(b?CHV:64);
          wait_prog(s_prog,min(rdy+BOFF,NITEMS));
          if(rdy+BOFF>NITEMS){
            if(tx==0) tx=gt();
            const long long until=tx+(long long)(rdy+LOFF-NITEMS)*10; int spins=0;
            while(gt()<until){ __nanosleep(50); if(++spins>(1<<22)) __trap(); }
          }
          if(!(ABL&32)) gather<16,4*DD>(oa,base+b*64*DD,min(16,(CHV-b*64-wg+3)/4),tag,100);
        }
      }
      sts128f(s_red+(2*NCS+wg)*512+lane*16,oa);
      if(TLI) tl_store(wg==3 && lane==0, &g_tl[20000*4+512+cta]);
      bar_sync(15,512);
      float a=lds32f(s_red+2*NCS*512+(tid&127)*4);
      #pragma unroll
      for(int i=1;i<4;i++) a+=lds32f(s_red+(2*NCS+i)*512+(tid&127)*4);
      #pragma unroll
      for(int i=0;i<2*NCS;i++) a+=lds32f(s_red+i*512+(tid&127)*4);
      out[obh*DD+ohalf*128+(tid&127)]=__float2bfloat16_rn(a);
    }
    if(TLI) tl_store((tid&127)==0, &g_tl[20000*4+cta]);
  } else {
    const uint32_t stage=sbase+grp*STAGE_BYTES, tw=s_tw+grp*512;
    const uint32_t bfull=s_full+grp*8, bside=s_side+grp*8;
    const int g=lane>>2, t=lane&3, qd=lane>>3, cc=lane&7;
    const int barid=1+grp;
    const int colo=cc*8+((lane>>4)&1)*4+((lane>>3)&1)*2;
    const uint32_t foff=OFF_SLICE+((lane&7)+((lane>>3)&1)*8)*128+(((2*wg+(lane>>4))^(lane&7))<<4);
    uint32_t ph=0; int item;
    __syncthreads();
    const unsigned tag=lds32(s_par);
    while(true){
      mbar_wait(bside,ph);
      item=(int)lds32(s_item+grp*4);
      if(item<0) break;
      if(item<NK){
        mbar_wait(bfull,ph);
        if(TLI) tl_store(wg==3 && lane==0, &g_tl[item*4+1]);
        float c[4]={0,0,0,0}, c2[4]={0,0,0,0};
        const uint32_t ra=stage+(wg*16+g)*512+t*16, qa=stage+OFF_Q+t*16;
        #pragma unroll
        for(int j=0;j<8;j++){
          const uint32_t co=((j^(g&1))*64);
          uint4 xa=lds128(ra+co), xb=lds128(ra+8*512+co), qv=lds128(qa+co);
          mma(c,xa.x,xb.x,xa.y,xb.y,qv.x,qv.y);
          mma(c2,xa.z,xb.z,xa.w,xb.w,qv.z,qv.w);
        }
        if(t==0){
          const float ta=(g&1)? c[1]+c2[1]:c[0]+c2[0], tb=(g&1)? c[3]+c2[3]:c[2]+c2[2];
          const int pos=(g>>1)*16+wg*4+(g&1);
          uint16_t ha=bf16_bits(ta), hb=bf16_bits(tb);
          sts16(tw+pos*2,ha); sts16(tw+(pos+2)*2,hb);
          sts16(tw+128+pos*2,bf16_bits(ta-bf_lo(ha))); sts16(tw+128+(pos+2)*2,bf16_bits(tb-bf_lo(hb)));
        }
        bar_sync(barid,128);
        uint4 b0=make_uint4(0,0,0,0), b1=b0;
        if(g<2){ b0=lds128(tw+g*128+t*32); b1=lds128(tw+g*128+t*32+16); }
        const uint32_t ea=stage+OFF_SLICE+(wg*16+(lane&7)+((lane>>3)&1)*8)*128;
        float d[4]={0,0,0,0};
        uint32_t a0,a1,a2,a3;
        ldsm4(ea+(((0+(lane>>4))^(lane&7))<<4),a0,a1,a2,a3); mma(d,a0,a1,a2,a3,b0.x,b0.y);
        ldsm4(ea+(((2+(lane>>4))^(lane&7))<<4),a0,a1,a2,a3); mma(d,a0,a1,a2,a3,b0.z,b0.w);
        ldsm4(ea+(((4+(lane>>4))^(lane&7))<<4),a0,a1,a2,a3); mma(d,a0,a1,a2,a3,b1.x,b1.y);
        ldsm4(ea+(((6+(lane>>4))^(lane&7))<<4),a0,a1,a2,a3); mma(d,a0,a1,a2,a3,b1.z,b1.w);
        const float hi8=__shfl_up_sync(~0u,d[2]+d[3],1);
        if(t<2) st_relaxed_f(&sc->spart[item*RR+wg*16+g+t*8], tagged(t? hi8 : d[0]+d[1], tag));
      } else {
        const int tile=vtile(item); const int bh=tile/CH;
        if(!(ABL&16)){ int n=0; while(lds_acquire(s_pready)<=(unsigned)bh){ __nanosleep(100); if(++n>(1<<22)) __trap(); } }
        uint4 p0=make_uint4(0,0,0,0), p1=p0;
        if(g<2){ p0=lds128(s_p+bh*256+g*128+t*32); p1=lds128(s_p+bh*256+g*128+t*32+16); }
        wslice(stage+foff,p0,p1,tw+wg*64,lane);
        bar_sync(barid,128);
        float acc[8]={0,0,0,0,0,0,0,0};
        mbar_wait(bfull,ph);
        if(TLI) tl_store(wg==3 && lane==0, &g_tl[item*4+1]);
        vrows<16,512>(acc,stage+qd*16*512+wg*128+cc*16,tw+qd*64);
        fold(acc,lane);
        st_relaxed_f2(&sc->opart[(size_t)tile*DD+wg*64+colo],tagged(acc[0],tag),tagged(acc[1],tag));
      }
      ph^=1;
      bar_sync(barid,128);
      if(wg==0 && lane==0) mbar_arrive(s_empty+grp*8);
      if(TLI==1){ tl_store(wg==3 && lane==0, &g_tl[item*4+2]); tl_store(wg==3 && lane==0, &g_tl[item*4+3]); }
    }
    if(owner){
      if(item!=IT_END){
        const int k=-2-item; const uint32_t buf= (SPARE && k==0)? sbase+NS*STAGE_BYTES : stage, cb=s_cbar+k*24;
        if(!(ABL&16)){ int n=0; while(lds_acquire(s_pready)<=(unsigned)obh){ __nanosleep(100); if(++n>(1<<22)) __trap(); } }
        uint4 p0=make_uint4(0,0,0,0), p1=p0;
        if(g<2){ p0=lds128(s_p+obh*256+g*128+t*32); p1=lds128(s_p+obh*256+g*128+t*32+16); }
        mbar_wait(cb,0);
        wslice(buf+foff,p0,p1,tw+wg*64,lane);
        wslice(buf+foff+8192,p0,p1,tw+256+wg*64,lane);
        bar_sync(barid,128);
        float acc[8]={0,0,0,0,0,0,0,0};
        const int row0=(wg>>1)*32+qd*8;
        const uint32_t va=buf+row0*256+(wg&1)*128+cc*16;
        mbar_wait(cb+8,0);
        vrows<8,256>(acc,va,tw+row0*4);
        mbar_wait(cb+16,0);
        if(TLI) tl_store(wg==3 && lane==0, &g_tl[(NITEMS+cta*NCS+k)*4+1]);
        vrows<8,256>(acc,va+16384,tw+256+row0*4);
        fold(acc,lane);
        sts64f(s_red+(k*2+(wg>>1))*512+((wg&1)*64+colo)*4,acc[0],acc[1]);
        if(TLI==1) tl_store(wg==3 && lane==0, &g_tl[(NITEMS+cta*NCS+k)*4+2]);
      }
      bar_arrive(15,512);
    }
  }
}

}

typedef CUresult (*EncFn)(CUtensorMap*, CUtensorMapDataType, cuuint32_t, void*, const cuuint64_t*, const cuuint64_t*, const cuuint32_t*, const cuuint32_t*, CUtensorMapInterleave, CUtensorMapSwizzle, CUtensorMapL2promotion, CUtensorMapFloatOOBfill);
static CUtensorMap make_map(EncFn fn, void* p, uint64_t cols, uint64_t rows, uint32_t bc, uint32_t br, CUtensorMapSwizzle sw){
  CUtensorMap m; cuuint64_t gd[2]={cols,rows}; cuuint64_t gs[1]={cols*2}; cuuint32_t bx[2]={bc,br}; cuuint32_t es[2]={1,1};
  fn(&m,CU_TENSOR_MAP_DATA_TYPE_BFLOAT16,2,p,gd,gs,bx,es,CU_TENSOR_MAP_INTERLEAVE_NONE,sw,CU_TENSOR_MAP_L2_PROMOTION_NONE,CU_TENSOR_MAP_FLOAT_OOB_FILL_NONE);
  return m;
}
extern "C" void kernel_launch(void* const* d_in, const int* in_sizes, int n_in, void* d_out, int out_size){
  static EncFn fn=nullptr; static int sms=0;
  const int smem=3*49*1024+64*256+3*512+10*512+512+1024;
  auto kern=v25::kern<0,700,3,330,0,0,0>;
  if(!fn){
    cudaDriverEntryPointQueryResult qr; void* f=nullptr;
    cudaGetDriverEntryPoint("cuTensorMapEncodeTiled",&f,cudaEnableDefault,&qr); fn=(EncFn)f;
    cudaDeviceGetAttribute(&sms,cudaDevAttrMultiProcessorCount,0);
    cudaFuncSetAttribute(kern,cudaFuncAttributeMaxDynamicSharedMemorySize,smem);
  }
  CUtensorMap e=make_map(fn,d_in[3],NN,RR,64,64,CU_TENSOR_MAP_SWIZZLE_128B), f=make_map(fn,d_in[4],NN,RR,64,64,CU_TENSOR_MAP_SWIZZLE_128B), v=make_map(fn,d_in[2],DD,(uint64_t)BH*NN,128,64,CU_TENSOR_MAP_SWIZZLE_NONE);
  kern<<<sms,640,smem>>>(e,f,v,(const char*)d_in[0],(const char*)d_in[1],(const char*)d_in[2],(const char*)d_in[4],(__nv_bfloat16*)d_out);
}
```

```cpp
#include <cuda_runtime.h>
#include <cuda_bf16.h>
#include <cuda.h>
#include <stdint.h>

namespace lf {

constexpr int BH = 64, NN = 8192, DD = 256, RR = 64;
constexpr int T = 64, CH = NN / T;
constexpr int NK = BH * CH;
constexpr int NS = 3;
constexpr int STAGE_BYTES = 41 * 1024;
constexpr int OFF_SLICE = 32768, OFF_Q = 40960;
constexpr int NHINT = 8;
constexpr int THREADS = 640;

struct Scratch {
    float spart[BH * CH * RR];
    float opart[BH * CH * DD];
    float w[BH * NN];
    float p[BH * RR];
    unsigned ctr[32];
    unsigned hint[2][2 * NHINT * 32];
};
__device__ __align__(1024) Scratch g_scratch;

__device__ __forceinline__ uint32_t smem_u32(const void* p) { return (uint32_t)__cvta_generic_to_shared(p); }
__device__ __forceinline__ float bf_lo(uint32_t x) { return __uint_as_float(x << 16); }
__device__ __forceinline__ float bf_hi(uint32_t x) { return __uint_as_float(x & 0xffff0000u); }
__device__ __forceinline__ uint16_t bf16_bits(float x) { return __bfloat16_as_ushort(__float2bfloat16_rn(x)); }
__device__ __forceinline__ void mbar_init(uint32_t bar, uint32_t cnt) { asm volatile("mbarrier.init.shared::cta.b64 [%0], %1;" ::"r"(bar), "r"(cnt) : "memory"); }
__device__ __forceinline__ void mbar_init_fence() { asm volatile("fence.mbarrier_init.release.cluster;" ::: "memory"); }
__device__ __forceinline__ void mbar_expect_tx(uint32_t bar, uint32_t bytes) { asm volatile("mbarrier.arrive.expect_tx.shared::cta.b64 _, [%0], %1;" ::"r"(bar), "r"(bytes) : "memory"); }
__device__ __forceinline__ void mbar_arrive(uint32_t bar) { asm volatile("mbarrier.arrive.shared::cta.b64 _, [%0];" ::"r"(bar) : "memory"); }
__device__ __forceinline__ bool mbar_try(uint32_t bar, uint32_t parity) {
    uint32_t ok;
    asm volatile("{\n.reg .pred p;\nmbarrier.try_wait.parity.shared::cta.b64 p, [%1], %2;\nselp.u32 %0,1,0,p;\n}" : "=r"(ok) : "r"(bar), "r"(parity) : "memory");
    return ok;
}
__device__ __forceinline__ void mbar_wait(uint32_t bar, uint32_t parity) {
    if (mbar_try(bar, parity)) return;
    const long long t0 = clock64();
    while (!mbar_try(bar, parity)) { if (clock64() - t0 > 4000000000ll) __trap(); }
}
constexpr uint64_t EVICT_FIRST = 0x12F0000000000000ull;
__device__ __forceinline__ void bulk_load(uint32_t dst, const void* src, uint32_t bytes, uint32_t bar) {
    asm volatile("cp.async.bulk.shared::cluster.global.mbarrier::complete_tx::bytes [%0], [%1], %2, [%3];" ::"r"(dst), "l"(src), "r"(bytes), "r"(bar) : "memory");
}
__device__ __forceinline__ void bulk_load_stream(uint32_t dst, const void* src, uint32_t bytes, uint32_t bar) {
    asm volatile("cp.async.bulk.shared::cluster.global.mbarrier::complete_tx::bytes.L2::cache_hint [%0], [%1], %2, [%3], %4;" ::"r"(dst), "l"(src), "r"(bytes), "r"(bar), "l"(EVICT_FIRST) : "memory");
}
__device__ __forceinline__ void tma2d(uint32_t dst, const CUtensorMap* tm, int c0, int c1, uint32_t bar) {
    asm volatile("cp.async.bulk.tensor.2d.shared::cluster.global.mbarrier::complete_tx::bytes [%0], [%1, {%3, %4}], [%2];" ::"r"(dst), "l"(tm), "r"(bar), "r"(c0), "r"(c1) : "memory");
}
__device__ __forceinline__ void tma2d_stream(uint32_t dst, const CUtensorMap* tm, int c0, int c1, uint32_t bar) {
    asm volatile("cp.async.bulk.tensor.2d.shared::cluster.global.mbarrier::complete_tx::bytes.L2::cache_hint [%0], [%1, {%3, %4}], [%2], %5;" ::"r"(dst), "l"(tm), "r"(bar), "r"(c0), "r"(c1), "l"(EVICT_FIRST) : "memory");
}
__device__ __forceinline__ void prefetch_l2(const void* p, uint32_t bytes) { asm volatile("cp.async.bulk.prefetch.L2.global [%0], %1;" ::"l"(p), "r"(bytes) : "memory"); }
__device__ __forceinline__ void prefetch_map(const CUtensorMap* tm) { asm volatile("prefetch.tensormap [%0];" ::"l"(tm) : "memory"); }
__device__ __forceinline__ uint4 lds128(uint32_t a) { uint4 v; asm volatile("ld.shared.v4.u32 {%0,%1,%2,%3}, [%4];" : "=r"(v.x), "=r"(v.y), "=r"(v.z), "=r"(v.w) : "r"(a)); return v; }
__device__ __forceinline__ float4 lds128f(uint32_t a) { float4 v; asm volatile("ld.shared.v4.f32 {%0,%1,%2,%3}, [%4];" : "=f"(v.x), "=f"(v.y), "=f"(v.z), "=f"(v.w) : "r"(a)); return v; }
__device__ __forceinline__ float lds32f(uint32_t a) { float v; asm volatile("ld.shared.f32 %0, [%1];" : "=f"(v) : "r"(a)); return v; }
__device__ __forceinline__ unsigned lds32(uint32_t a) { unsigned v; asm volatile("ld.volatile.shared.u32 %0, [%1];" : "=r"(v) : "r"(a) : "memory"); return v; }
__device__ __forceinline__ unsigned lds_acquire(uint32_t a) { unsigned v; asm volatile("ld.acquire.cta.shared.u32 %0, [%1];" : "=r"(v) : "r"(a) : "memory"); return v; }
__device__ __forceinline__ void sts_release(uint32_t a, unsigned v) { asm volatile("st.release.cta.shared.u32 [%0], %1;" ::"r"(a), "r"(v) : "memory"); }
__device__ __forceinline__ void sts32(uint32_t a, unsigned v) { asm volatile("st.volatile.shared.u32 [%0], %1;" ::"r"(a), "r"(v) : "memory"); }
__device__ __forceinline__ void sts16(uint32_t a, uint16_t v) { asm volatile("st.shared.u16 [%0], %1;" ::"r"(a), "h"(v) : "memory"); }
__device__ __forceinline__ void sts64f(uint32_t a, float x, float y) { asm volatile("st.shared.v2.f32 [%0], {%1,%2};" ::"r"(a), "f"(x), "f"(y) : "memory"); }
__device__ __forceinline__ void sts128f(uint32_t a, float4 v) { asm volatile("st.shared.v4.f32 [%0], {%1,%2,%3,%4};" ::"r"(a), "f"(v.x), "f"(v.y), "f"(v.z), "f"(v.w) : "memory"); }
__device__ __forceinline__ unsigned atoms_inc(uint32_t a) { unsigned v; asm volatile("atom.relaxed.cta.shared.add.u32 %0, [%1], 1;" : "=r"(v) : "r"(a) : "memory"); return v; }
__device__ __forceinline__ void ldsm4(uint32_t a, uint32_t& r0, uint32_t& r1, uint32_t& r2, uint32_t& r3) {
    asm volatile("ldmatrix.sync.aligned.m8n8.x4.shared.b16 {%0,%1,%2,%3}, [%4];" : "=r"(r0), "=r"(r1), "=r"(r2), "=r"(r3) : "r"(a));
}
__device__ __forceinline__ void ldsm4t(uint32_t a, uint32_t& r0, uint32_t& r1, uint32_t& r2, uint32_t& r3) {
    asm volatile("ldmatrix.sync.aligned.m8n8.x4.trans.shared.b16 {%0,%1,%2,%3}, [%4];" : "=r"(r0), "=r"(r1), "=r"(r2), "=r"(r3) : "r"(a));
}
__device__ __forceinline__ void mma(float (&c)[4], uint32_t a0, uint32_t a1, uint32_t a2, uint32_t a3, uint32_t b0, uint32_t b1) {
    asm volatile("mma.sync.aligned.m16n8k16.row.col.f32.bf16.bf16.f32 {%0,%1,%2,%3}, {%4,%5,%6,%7}, {%8,%9}, {%0,%1,%2,%3};"
                 : "+f"(c[0]), "+f"(c[1]), "+f"(c[2]), "+f"(c[3]) : "r"(a0), "r"(a1), "r"(a2), "r"(a3), "r"(b0), "r"(b1));
}
__device__ __forceinline__ void bar_sync(int id, int n) { __syncwarp(); asm volatile("bar.sync %0, %1;" ::"r"(id), "r"(n) : "memory"); }
__device__ __forceinline__ void bar_arrive(int id, int n) { __syncwarp(); asm volatile("bar.arrive %0, %1;" ::"r"(id), "r"(n) : "memory"); }
__device__ __forceinline__ void red_inc(unsigned* p) { asm volatile("red.relaxed.gpu.global.add.u32 [%0], 1;" ::"l"(p) : "memory"); }
__device__ __forceinline__ unsigned atom_inc(unsigned* p) { unsigned v; asm volatile("atom.relaxed.gpu.global.add.u32 %0, [%1], 1;" : "=r"(v) : "l"(p) : "memory"); return v; }
__device__ __forceinline__ unsigned atom_inc_wrap(unsigned* p, unsigned last) { unsigned v; asm volatile("atom.relaxed.gpu.global.inc.u32 %0, [%1], %2;" : "=r"(v) : "l"(p), "r"(last) : "memory"); return v; }
__device__ __forceinline__ unsigned ld_relaxed(const unsigned* p) { unsigned v; asm volatile("ld.relaxed.gpu.global.u32 %0, [%1];" : "=r"(v) : "l"(p) : "memory"); return v; }
__device__ __forceinline__ void st_relaxed(unsigned* p, unsigned v) { asm volatile("st.relaxed.gpu.global.u32 [%0], %1;" ::"l"(p), "r"(v) : "memory"); }
__device__ __forceinline__ float ld_relaxed_f(const float* p) { float v; asm volatile("ld.relaxed.gpu.global.f32 %0, [%1];" : "=f"(v) : "l"(p) : "memory"); return v; }
__device__ __forceinline__ float4 ld_relaxed_f4(const float* p) { float4 v; asm volatile("ld.relaxed.gpu.global.v4.f32 {%0,%1,%2,%3}, [%4];" : "=f"(v.x), "=f"(v.y), "=f"(v.z), "=f"(v.w) : "l"(p) : "memory"); return v; }
__device__ __forceinline__ void st_relaxed_f(float* p, float v) { asm volatile("st.relaxed.gpu.global.f32 [%0], %1;" ::"l"(p), "f"(v) : "memory"); }
__device__ __forceinline__ void st_relaxed_f2(float* p, float a, float b) { asm volatile("st.relaxed.gpu.global.v2.f32 [%0], {%1,%2};" ::"l"(p), "f"(a), "f"(b) : "memory"); }
__device__ __forceinline__ void st_relaxed_f4(float* p, float4 v) { asm volatile("st.relaxed.gpu.global.v4.f32 [%0], {%1,%2,%3,%4};" ::"l"(p), "f"(v.x), "f"(v.y), "f"(v.z), "f"(v.w) : "memory"); }

__device__ __forceinline__ float tagged(float x, unsigned tag) { return __uint_as_float((__float_as_uint(x) & ~1u) | tag); }
__device__ __forceinline__ float untag(float x) { return __uint_as_float(__float_as_uint(x) & ~1u); }
__device__ __forceinline__ bool tag_ok(const float4& v, unsigned tag) {
    return (((__float_as_uint(v.x) ^ tag) | (__float_as_uint(v.y) ^ tag) | (__float_as_uint(v.z) ^ tag) | (__float_as_uint(v.w) ^ tag)) & 1u) == 0;
}
template <int STRIDE>
__device__ __forceinline__ void gather16(float4& acc, const float* base, int n, unsigned tag, int sleep_ns) {
    int spins = 0;
    unsigned pend = (1u << n) - 1u;
    float4 v[16];
#pragma unroll
    for (int i = 0; i < 16; i++) v[i] = make_float4(0.f, 0.f, 0.f, 0.f);
    while (true) {
#pragma unroll
        for (int i = 0; i < 16; i++)
            asm volatile("{\n.reg .pred p;\nsetp.ne.u32 p, %5, 0;\n@p ld.relaxed.gpu.global.v4.f32 {%0,%1,%2,%3}, [%4];\n}"
                         : "+f"(v[i].x), "+f"(v[i].y), "+f"(v[i].z), "+f"(v[i].w) : "l"(base + i * STRIDE), "r"(pend & (1u << i)) : "memory");
        unsigned bad = 0;
#pragma unroll
        for (int i = 0; i < 16; i++) bad |= tag_ok(v[i], tag) ? 0u : (1u << i);
        pend &= __reduce_or_sync(~0u, bad);
        if (!pend) break;
        __nanosleep(sleep_ns);
        if (++spins > (1 << 23)) __trap();
    }
#pragma unroll
    for (int i = 0; i < 16; i++) { acc.x += untag(v[i].x); acc.y += untag(v[i].y); acc.z += untag(v[i].z); acc.w += untag(v[i].w); }
}
__device__ __forceinline__ void wait_prog(uint32_t a, int thr) {
    int spins = 0;
    while ((int)lds32(a) < thr - 1500) { __nanosleep(1000); if (++spins > (1 << 22)) __trap(); }
    while ((int)lds32(a) < thr) { __nanosleep(100); if (++spins > (1 << 24)) __trap(); }
}
__device__ __forceinline__ void wait_above(uint32_t a, unsigned v, int sleep_ns) {
    int spins = 0;
    while (lds_acquire(a) <= v) { __nanosleep(sleep_ns); if (++spins > (1 << 24)) __trap(); }
}

template <int ROWS, int PITCH>
__device__ __forceinline__ void vrows(float (&acc)[8], uint32_t va, uint32_t wa) {
#pragma unroll
    for (int i4 = 0; i4 < ROWS / 4; i4++) {
        const float4 w4 = lds128f(wa + i4 * 16);
        const float wv[4] = {untag(w4.x), untag(w4.y), untag(w4.z), untag(w4.w)};
#pragma unroll
        for (int i = 0; i < 4; i++) {
            const uint4 x = lds128(va + (i4 * 4 + i) * PITCH);
            acc[0] = fmaf(wv[i], bf_lo(x.x), acc[0]); acc[1] = fmaf(wv[i], bf_hi(x.x), acc[1]);
            acc[2] = fmaf(wv[i], bf_lo(x.y), acc[2]); acc[3] = fmaf(wv[i], bf_hi(x.y), acc[3]);
            acc[4] = fmaf(wv[i], bf_lo(x.z), acc[4]); acc[5] = fmaf(wv[i], bf_hi(x.z), acc[5]);
            acc[6] = fmaf(wv[i], bf_lo(x.w), acc[6]); acc[7] = fmaf(wv[i], bf_hi(x.w), acc[7]);
        }
    }
}
__device__ __forceinline__ void fold(float (&acc)[8], int lane) {
    {
        const bool hi = lane & 16;
#pragma unroll
        for (int i = 0; i < 4; i++) { const float snd = hi ? acc[i] : acc[i + 4], kp = hi ? acc[i + 4] : acc[i]; acc[i] = kp + __shfl_xor_sync(~0u, snd, 16); }
    }
    {
        const bool hi = lane & 8;
#pragma unroll
        for (int i = 0; i < 2; i++) { const float snd = hi ? acc[i] : acc[i + 2], kp = hi ? acc[i + 2] : acc[i]; acc[i] = kp + __shfl_xor_sync(~0u, snd, 8); }
    }
}

template <int NPC, int NLATE>
struct Plan {
    static constexpr int XROWS = NPC * 64;
    static constexpr int CHV = (NN - XROWS) / T;
    static constexpr int LB = BH - NLATE;
    static constexpr int NVA = LB * CHV;
    static constexpr int NITEMS = NK + NVA + NLATE * CH;
    static constexpr int NCL = (NPC + 1) / 2;
    static constexpr int NRED = 2 * NCL + 4;
    static constexpr int SMEM = NS * STAGE_BYTES + 8192 + 8 * 256 + NS * 1024 + NRED * 512 + 256 + 1024;
    static_assert(NCL <= NS && NLATE <= NHINT && NPC % 2 == 0, "plan");
};

template <int NPC, int NLATE, int BOFF, int ZT, int HOLD, int TD>
__global__ void __launch_bounds__(THREADS, 1)
linformer_kernel(const __grid_constant__ CUtensorMap tmE, const __grid_constant__ CUtensorMap tmF,
                 const __grid_constant__ CUtensorMap tmV, const __grid_constant__ CUtensorMap tmC,
                 const char* __restrict__ q, const char* __restrict__ K, const char* __restrict__ V,
                 __nv_bfloat16* __restrict__ out, Scratch* __restrict__ sc) {
    using P = Plan<NPC, NLATE>;
    constexpr int XROWS = P::XROWS, CHV = P::CHV, LB = P::LB, NVA = P::NVA, NITEMS = P::NITEMS, NCL = P::NCL;
    constexpr int NSTAT = 2 * NS;
    constexpr int LBH = BH - NHINT;
    constexpr int IT_END = -1;
    extern __shared__ __align__(1024) char smem_raw[];
    const uint32_t sbase = (smem_u32(smem_raw) + 1023u) & ~1023u;
    const uint32_t s_f = sbase + NS * STAGE_BYTES;
    const uint32_t s_p = s_f + 8192;
    const uint32_t s_tw = s_p + 8 * 256;
    const uint32_t s_red = s_tw + NS * 1024;
    const uint32_t s_full = s_red + P::NRED * 512;
    const uint32_t s_side = s_full + NS * 8;
    const uint32_t s_empty = s_side + NS * 8;
    const uint32_t s_cbar = s_empty + NS * 8;
    const uint32_t s_item = s_cbar + 8 * 8;
    const uint32_t s_tag = s_item + NS * 4;
    const uint32_t s_prog = s_tag + 4;
    const uint32_t s_fail = s_prog + 4;
    if (threadIdx.x == 16 * 32) {
        mbar_init(s_full, 1);
        mbar_init_fence();
        mbar_expect_tx(s_full, 32768);
        bulk_load_stream(sbase, K + (size_t)blockIdx.x * 32768, 32768, s_full);
#pragma unroll
        for (int g = 0; g < NS; g++) { if (g) mbar_init(s_full + g * 8, 1); mbar_init(s_side + g * 8, 1); mbar_init(s_empty + g * 8, 1); }
        mbar_init_fence();
#pragma unroll
        for (int g = 0; g < NS; g++) {
            const int tile = g * gridDim.x + blockIdx.x;
            const uint32_t stage = sbase + g * STAGE_BYTES;
            sts32(s_item + g * 4, tile);
            if (g) { mbar_expect_tx(s_full + g * 8, 32768); bulk_load_stream(stage, K + (size_t)tile * 32768, 32768, s_full + g * 8); }
            mbar_expect_tx(s_side + g * 8, 8192 + 512);
            tma2d(stage + OFF_SLICE, &tmE, (tile & (CH - 1)) * T, 0, s_side + g * 8);
            bulk_load(stage + OFF_Q, q + (tile / CH) * 512, 512, s_side + g * 8);
        }
    }
    if (threadIdx.x == (16 + NS) * 32 + 1) prefetch_map(&tmE);
    const int tid = threadIdx.x, warp = tid >> 5, lane = tid & 31;
    const int grp = warp >> 2, wg = warp & 3;
    const int nCTA = gridDim.x, cta = blockIdx.x;
    const bool owner = cta < 2 * BH;
    const int obh = cta >> 1, ohalf = cta & 1;
    const bool closes = owner && obh < LB;
    auto get_tag = [&]() {
        wait_above(s_tag, 1, 20);
        return lds32(s_tag) & 1u;
    };
    auto vtile = [](int item) { const int j = item - NK; if (j >= NVA) return LB * CH + (j - NVA); const int bh = j / CHV; return bh * CH + (j - bh * CHV); };

    if (warp >= 16 && warp < 16 + NS) {
        const int st = warp - 16;
        const uint32_t stage = sbase + st * STAGE_BYTES, bfull = s_full + st * 8, bside = s_side + st * 8, bempty = s_empty + st * 8;
        auto put = [&](int item) {
            mbar_expect_tx(bfull, 32768);
            if (item < NK) {
                bulk_load_stream(stage, K + (size_t)item * 32768, 32768, bfull);
                mbar_expect_tx(bside, 8192 + 512);
                tma2d(stage + OFF_SLICE, &tmE, (item & (CH - 1)) * T, 0, bside);
                bulk_load(stage + OFF_Q, q + (item / CH) * 512, 512, bside);
            } else {
                const int tile = vtile(item);
                tma2d_stream(stage, &tmV, (tile & 1) * 128, (tile >> 1) * 128, bfull);
                mbar_expect_tx(bside, 512);
                bulk_load(stage + OFF_SLICE, &sc->w[(tile >> 1) * 128], 512, bside);
            }
        };
        __syncthreads();
        if (lane == 0) {
            int item = (NS + st) * nCTA + cta;
            uint32_t ph = 0;
            bool warmed = !closes;
            mbar_wait(bempty, ph);
            unsigned* ticket = nullptr;
            while (true) {
                sts32(s_item + st * 4, item);
                put(item);
                ph ^= 1;
                if (!warmed && item >= NITEMS - ZT) {
                    warmed = true;
                    prefetch_l2(V + ((size_t)(obh * NN + NN - XROWS + (st < NCL ? st : 0) * 128) * 512 + ohalf * 256), 128);
                }
                mbar_wait(bempty, ph);
                if (TD && item >= NK) { const long long t0 = clock64(); while (clock64() - t0 < TD) __nanosleep(20); }
                if (!ticket) ticket = &sc->ctr[1 + get_tag()];
                item = NSTAT * nCTA + (int)atom_inc(ticket);
                if (item > (int)lds32(s_prog)) sts32(s_prog, item);
                if (item >= NITEMS) break;
            }
            const int f = closes ? (int)atoms_inc(s_fail) : NS;
            if (f < NCL) {
                if (f < 2) {
                    const long long t0 = clock64();
                    while (clock64() - t0 < (HOLD >> f)) __nanosleep(20);
                }
                const int row = obh * NN + NN - XROWS + f * 128;
                mbar_expect_tx(s_cbar + 2 * f * 8, 16384 + 512);
                bulk_load(stage + OFF_SLICE, &sc->w[row], 512, s_cbar + 2 * f * 8);
                tma2d_stream(stage, &tmC, ohalf * 128, row, s_cbar + 2 * f * 8);
                mbar_expect_tx(s_cbar + (2 * f + 1) * 8, 16384);
                tma2d_stream(stage + 16384, &tmC, ohalf * 128, row + 64, s_cbar + (2 * f + 1) * 8);
            }
            sts32(s_item + st * 4, f < NCL ? -2 - f : IT_END);
            mbar_arrive(bside);
        }
    } else if (warp == 16 + NS) {
        if (lane == 0) { sts32(s_tag, 0); sts32(s_prog, 0); sts32(s_fail, 0); }
        if (lane == 2) {
#pragma unroll
            for (int i = 0; i < NPC + 1; i++) mbar_init(s_cbar + i * 8, 1);
            mbar_init_fence();
        }
        unsigned arrived = 0;
        if (lane == 0) arrived = atom_inc_wrap(&sc->ctr[0], 2 * nCTA - 1);
        __syncthreads();
        if (lane == 0) sts_release(s_tag, arrived < (unsigned)nCTA ? 3u : 2u);
        __syncwarp();
        const unsigned tag = get_tag();
        if (cta == 0) {
            if (lane == 0) st_relaxed(&sc->ctr[1 + (tag ^ 1)], 0);
            if (lane < 2 * NHINT) sc->hint[tag ^ 1][lane * 32] = 0;
        }
        wait_prog(s_prog, NK - 3000);
        if (lane == 0) {
            prefetch_map(&tmV); prefetch_map(&tmC);
            if (owner) { mbar_expect_tx(s_cbar + NPC * 8, 8192); tma2d(s_f, &tmF, cta * 64, 0, s_cbar + NPC * 8); }
        }
        __syncwarp();
        wait_prog(s_prog, NK - 1536);
        const int pos = ((lane >> 1) & 3) * 16 + (lane >> 4) * 4 + ((lane >> 3) & 1) * 2 + (lane & 1);
        for (int b0 = 0; b0 < BH && owner; b0 += 8) {
            float v0[8], v1[8];
            int done = 0, spins = 0;
            wait_prog(s_prog, (b0 + 8) * CH + BOFF + 300);
            while (true) {
#pragma unroll
                for (int i = 0; i < 8; i++)
                    if (i >= done) { v0[i] = ld_relaxed_f(&sc->p[(b0 + i) * RR + lane]); v1[i] = ld_relaxed_f(&sc->p[(b0 + i) * RR + 32 + lane]); }
#pragma unroll
                for (int i = 0; i < 8; i++)
                    if (i == done && __all_sync(~0u, (((__float_as_uint(v0[i]) ^ tag) | (__float_as_uint(v1[i]) ^ tag)) & 1u) == 0)) {
                        const uint32_t pb = s_p + i * 256;
                        const float x0 = untag(v0[i]), x1 = untag(v1[i]);
                        const uint16_t h0 = bf16_bits(x0), h1 = bf16_bits(x1);
                        sts16(pb + pos * 2, h0); sts16(pb + (pos + 8) * 2, h1);
                        sts16(pb + 128 + pos * 2, bf16_bits(x0 - bf_lo(h0))); sts16(pb + 128 + (pos + 8) * 2, bf16_bits(x1 - bf_lo(h1)));
                        done++;
                    }
                if (done == 8) break;
                __nanosleep(1000);
                if (++spins > (1 << 22)) __trap();
            }
            __syncwarp();
            if (b0 == 0) mbar_wait(s_cbar + NPC * 8, 0);
            const int g = lane >> 2, t = lane & 3;
            const uint32_t pa = s_p + (g >> 1) * 256 + (g & 1) * 128 + t * 32;
            const uint4 l0 = lds128(pa), l1 = lds128(pa + 16), u0 = lds128(pa + 1024), u1 = lds128(pa + 1024 + 16);
            __syncwarp();
            float* wp = &sc->w[(size_t)(b0 + (g >> 1) + (g & 1) * 4) * NN + cta * 64 + 2 * t];
#pragma unroll
            for (int jp = 0; jp < 4; jp++) {
                const uint32_t fa = s_f + ((lane & 7) + ((lane >> 3) & 1) * 8) * 128 + (((2 * jp + (lane >> 4)) ^ (lane & 7)) << 4);
                float d0[4] = {0.f, 0.f, 0.f, 0.f}, d1[4] = {0.f, 0.f, 0.f, 0.f};
                uint32_t m0, m1, m2, m3;
                ldsm4t(fa + 0 * 2048, m0, m1, m2, m3); mma(d0, l0.x, u0.x, l0.y, u0.y, m0, m1); mma(d1, l0.x, u0.x, l0.y, u0.y, m2, m3);
                ldsm4t(fa + 1 * 2048, m0, m1, m2, m3); mma(d0, l0.z, u0.z, l0.w, u0.w, m0, m1); mma(d1, l0.z, u0.z, l0.w, u0.w, m2, m3);
                ldsm4t(fa + 2 * 2048, m0, m1, m2, m3); mma(d0, l1.x, u1.x, l1.y, u1.y, m0, m1); mma(d1, l1.x, u1.x, l1.y, u1.y, m2, m3);
                ldsm4t(fa + 3 * 2048, m0, m1, m2, m3); mma(d0, l1.z, u1.z, l1.w, u1.w, m0, m1); mma(d1, l1.z, u1.z, l1.w, u1.w, m2, m3);
#pragma unroll
                for (int i = 0; i < 4; i++) { d0[i] += __shfl_xor_sync(~0u, d0[i], 4); d1[i] += __shfl_xor_sync(~0u, d1[i], 4); }
                const bool up = g & 1;
                st_relaxed_f2(wp + jp * 16, tagged(up ? d0[2] : d0[0], tag), tagged(up ? d0[3] : d0[1], tag));
                st_relaxed_f2(wp + jp * 16 + 8, tagged(up ? d1[2] : d1[0], tag), tagged(up ? d1[3] : d1[1], tag));
            }
        }
    } else if (grp == NS) {
        __syncthreads();
        if (owner) {
            const unsigned tag = get_tag();
            if (ohalf == 0) {
                wait_prog(s_prog, (obh + 1) * CH + BOFF);
                float4 a = make_float4(0.f, 0.f, 0.f, 0.f);
                gather16<128>(a, &sc->spart[((size_t)obh * CH + wg * 32) * RR + lane * 4], 16, tag, 500);
                sts128f(s_red + wg * 512 + lane * 16, a);
                bar_sync(4, 128);
                if (wg == 0) {
                    a = lds128f(s_red + (lane & 15) * 16);
#pragma unroll
                    for (int i = 1; i < 8; i++) { const float4 b = lds128f(s_red + i * 256 + (lane & 15) * 16); a.x += b.x; a.y += b.y; a.z += b.z; a.w += b.w; }
                    a.x *= 0.0625f; a.y *= 0.0625f; a.z *= 0.0625f; a.w *= 0.0625f;
                    float mx = fmaxf(fmaxf(a.x, a.y), fmaxf(a.z, a.w));
#pragma unroll
                    for (int o = 8; o; o >>= 1) mx = fmaxf(mx, __shfl_xor_sync(~0u, mx, o));
                    a.x = __expf(a.x - mx); a.y = __expf(a.y - mx); a.z = __expf(a.z - mx); a.w = __expf(a.w - mx);
                    float z = (a.x + a.y) + (a.z + a.w);
#pragma unroll
                    for (int o = 8; o; o >>= 1) z += __shfl_xor_sync(~0u, z, o);
                    const float iz = 1.0f / z;
                    if (lane < 16) st_relaxed_f4(&sc->p[obh * RR + lane * 4], make_float4(tagged(a.x * iz, tag), tagged(a.y * iz, tag), tagged(a.z * iz, tag), tagged(a.w * iz, tag)));
                }
                bar_sync(4, 128);
            }
            const int ocnt = obh < LB ? CHV / 2 : CH / 2;
            const int rdy = (obh < LB ? NK + obh * CHV : NK + NVA + (obh - LB) * CH) + 2 * ocnt;
            float4 oa = make_float4(0.f, 0.f, 0.f, 0.f);
            if (obh < LBH) {
                wait_prog(s_prog, rdy + BOFF);
            } else {
                wait_prog(s_prog, min(rdy + 150, NITEMS));
                const unsigned* hp = &sc->hint[tag][((obh - LBH) * 2 + ohalf) * 32];
                int spins = 0;
                while (ld_relaxed(hp) < (unsigned)ocnt) { __nanosleep(60); if (++spins > (1 << 24)) __trap(); }
            }
            gather16<4 * 128>(oa, &sc->opart[((size_t)cta * 64 + wg) * 128 + lane * 4], min(16, (ocnt - wg + 3) / 4), tag, 100);
            sts128f(s_red + (2 * NCL + wg) * 512 + lane * 16, oa);
            bar_sync(15, 512);
            const uint32_t ra = s_red + (tid & 127) * 4;
            float a = (lds32f(ra + 2 * NCL * 512) + lds32f(ra + (2 * NCL + 1) * 512)) + (lds32f(ra + (2 * NCL + 2) * 512) + lds32f(ra + (2 * NCL + 3) * 512));
            if (closes) {
#pragma unroll
                for (int i = 0; i < 2 * NCL; i++) a += lds32f(ra + i * 512);
            }
            out[obh * DD + ohalf * 128 + (tid & 127)] = __float2bfloat16_rn(a);
        }
    } else {
        const uint32_t stage = sbase + grp * STAGE_BYTES, tw = s_tw + grp * 1024;
        const uint32_t bfull = s_full + grp * 8, bside = s_side + grp * 8;
        const int g = lane >> 2, t = lane & 3, qd = lane >> 3, cc = lane & 7;
        const int barid = 1 + grp;
        const int colo = cc * 8 + ((lane >> 4) & 1) * 4 + ((lane >> 3) & 1) * 2;
        unsigned tag = 2u;
        uint32_t ph = 0;
        int item;
        auto check_w = [&](uint32_t dst, const float* src) {
            float4 v = lds128f(dst + lane * 16);
            if (__all_sync(~0u, tag_ok(v, tag))) return;
            int spins = 0;
            do { __nanosleep(200); if (++spins > (1 << 23)) __trap(); v = ld_relaxed_f4(src + lane * 4); } while (!__all_sync(~0u, tag_ok(v, tag)));
            sts128f(dst + lane * 16, v);
            __syncwarp();
        };
        __syncthreads();
        while (true) {
            mbar_wait(bside, ph);
            item = (int)lds32(s_item + grp * 4);
            if (item < 0) break;
            if (item < NK) {
                mbar_wait(bfull, ph);
                float c[4] = {0.f, 0.f, 0.f, 0.f}, c2[4] = {0.f, 0.f, 0.f, 0.f};
                const uint32_t ra = stage + (wg * 16 + g) * 512 + t * 16, qa = stage + OFF_Q + t * 16;
#pragma unroll
                for (int j = 0; j < 8; j++) {
                    const uint32_t co = (j ^ (g & 1)) * 64;
                    const uint4 xa = lds128(ra + co), xb = lds128(ra + 8 * 512 + co), qv = lds128(qa + co);
                    mma(c, xa.x, xb.x, xa.y, xb.y, qv.x, qv.y);
                    mma(c2, xa.z, xb.z, xa.w, xb.w, qv.z, qv.w);
                }
                if (t == 0) {
                    const float ta = (g & 1) ? c[1] + c2[1] : c[0] + c2[0], tb = (g & 1) ? c[3] + c2[3] : c[2] + c2[2];
                    const int pos = (g >> 1) * 16 + wg * 4 + (g & 1);
                    const uint16_t ha = bf16_bits(ta), hb = bf16_bits(tb);
                    sts16(tw + pos * 2, ha); sts16(tw + (pos + 2) * 2, hb);
                    sts16(tw + 128 + pos * 2, bf16_bits(ta - bf_lo(ha))); sts16(tw + 128 + (pos + 2) * 2, bf16_bits(tb - bf_lo(hb)));
                }
                bar_sync(barid, 128);
                uint4 b0 = make_uint4(0, 0, 0, 0), b1 = b0;
                if (g < 2) { b0 = lds128(tw + g * 128 + t * 32); b1 = lds128(tw + g * 128 + t * 32 + 16); }
                const uint32_t ea = stage + OFF_SLICE + (wg * 16 + (lane & 7) + ((lane >> 3) & 1) * 8) * 128;
                float d[4] = {0.f, 0.f, 0.f, 0.f};
                uint32_t a0, a1, a2, a3;
                ldsm4(ea + (((0 + (lane >> 4)) ^ (lane & 7)) << 4), a0, a1, a2, a3); mma(d, a0, a1, a2, a3, b0.x, b0.y);
                ldsm4(ea + (((2 + (lane >> 4)) ^ (lane & 7)) << 4), a0, a1, a2, a3); mma(d, a0, a1, a2, a3, b0.z, b0.w);
                ldsm4(ea + (((4 + (lane >> 4)) ^ (lane & 7)) << 4), a0, a1, a2, a3); mma(d, a0, a1, a2, a3, b1.x, b1.y);
                ldsm4(ea + (((6 + (lane >> 4)) ^ (lane & 7)) << 4), a0, a1, a2, a3); mma(d, a0, a1, a2, a3, b1.z, b1.w);
                const float hi8 = __shfl_up_sync(~0u, d[2] + d[3], 1);
                bar_sync(barid, 128);
                if (wg == 0 && lane == 0) mbar_arrive(s_empty + grp * 8);
                if (tag == 2u) tag = get_tag();
                if (t < 2) st_relaxed_f(&sc->spart[item * RR + wg * 16 + g + t * 8], tagged(t ? hi8 : d[0] + d[1], tag));
            } else {
                const int tile = vtile(item), bh = tile / CH, row0 = (wg >> 1) * 64 + qd * 16;
                check_w(stage + OFF_SLICE, &sc->w[(tile >> 1) * 128]);
                float acc[8] = {0.f, 0.f, 0.f, 0.f, 0.f, 0.f, 0.f, 0.f};
                mbar_wait(bfull, ph);
                vrows<16, 256>(acc, stage + row0 * 256 + (wg & 1) * 128 + cc * 16, stage + OFF_SLICE + row0 * 4);
                fold(acc, lane);
                const uint32_t xb = tw + ph * 512 + (wg & 1) * 256 + lane * 8;
                if (wg >= 2) sts64f(xb, acc[0], acc[1]);
                bar_sync(barid, 128);
                if (wg == 3 && lane == 0) mbar_arrive(s_empty + grp * 8);
                if (wg < 2) {
                    const float ox = lds32f(xb), oy = lds32f(xb + 4);
                    st_relaxed_f2(&sc->opart[((size_t)(bh * 2 + (tile & 1)) * 64 + ((tile & (CH - 1)) >> 1)) * 128 + wg * 64 + colo], tagged(acc[0] + ox, tag), tagged(acc[1] + oy, tag));
                    if (bh >= LBH) { bar_sync(5 + grp, 64); if (wg == 0 && lane == 0) red_inc(&sc->hint[tag][((bh - LBH) * 2 + (tile & 1)) * 32]); }
                }
            }
            ph ^= 1;
        }
        if (owner) {
            if (item != IT_END) {
                const int f = -2 - item, row0 = (wg >> 1) * 32 + qd * 8;
                float acc[8] = {0.f, 0.f, 0.f, 0.f, 0.f, 0.f, 0.f, 0.f};
                const uint32_t va = stage + row0 * 256 + (wg & 1) * 128 + cc * 16, wa = stage + OFF_SLICE + row0 * 4;
                mbar_wait(s_cbar + 2 * f * 8, 0);
                check_w(stage + OFF_SLICE, &sc->w[obh * NN + NN - XROWS + f * 128]);
                vrows<8, 256>(acc, va, wa);
                mbar_wait(s_cbar + (2 * f + 1) * 8, 0);
                vrows<8, 256>(acc, va + 16384, wa + 256);
                fold(acc, lane);
                sts64f(s_red + (f * 2 + (wg >> 1)) * 512 + ((wg & 1) * 64 + colo) * 4, acc[0], acc[1]);
            }
            bar_arrive(15, 512);
        }
    }
}

__global__ void __launch_bounds__(256) fb_scores(const __nv_bfloat16* q, const __nv_bfloat16* K, const __nv_bfloat16* E, Scratch* sc) {
    __shared__ float t[T];
    const int tile = blockIdx.x, bh = tile / CH, n0 = (tile % CH) * T, warp = threadIdx.x >> 5, lane = threadIdx.x & 31;
    for (int r = warp; r < T; r += 8) {
        float a = 0.f;
        for (int d = lane; d < DD; d += 32) a += __bfloat162float(K[((size_t)tile * T + r) * DD + d]) * __bfloat162float(q[bh * DD + d]);
        for (int o = 16; o; o >>= 1) a += __shfl_xor_sync(~0u, a, o);
        if (lane == 0) t[r] = a;
    }
    __syncthreads();
    if (threadIdx.x < RR) {
        float a = 0.f;
        for (int n = 0; n < T; n++) a += __bfloat162float(E[(size_t)threadIdx.x * NN + n0 + n]) * t[n];
        sc->spart[tile * RR + threadIdx.x] = a;
    }
}
__global__ void __launch_bounds__(64) fb_softmax(Scratch* sc) {
    __shared__ float s[RR];
    const int bh = blockIdx.x, r = threadIdx.x;
    float a = 0.f;
    for (int c = 0; c < CH; c++) a += sc->spart[(bh * CH + c) * RR + r];
    s[r] = a * 0.0625f;
    __syncthreads();
    float m = s[0], z = 0.f;
    for (int i = 1; i < RR; i++) m = fmaxf(m, s[i]);
    for (int i = 0; i < RR; i++) z += __expf(s[i] - m);
    sc->p[bh * RR + r] = __expf(s[r] - m) / z;
}
__global__ void __launch_bounds__(256) fb_values(const __nv_bfloat16* V, const __nv_bfloat16* F, Scratch* sc) {
    __shared__ float w[T];
    const int tile = blockIdx.x, bh = tile / CH, n0 = (tile % CH) * T, d = threadIdx.x;
    if (d < T) {
        float a = 0.f;
        for (int r = 0; r < RR; r++) a += sc->p[bh * RR + r] * __bfloat162float(F[(size_t)r * NN + n0 + d]);
        w[d] = a;
    }
    __syncthreads();
    float a = 0.f;
    for (int n = 0; n < T; n++) a += w[n] * __bfloat162float(V[((size_t)tile * T + n) * DD + d]);
    sc->opart[(size_t)tile * DD + d] = a;
}
__global__ void __launch_bounds__(256) fb_final(Scratch* sc, __nv_bfloat16* out) {
    float a = 0.f;
    for (int c = 0; c < CH; c++) a += sc->opart[((size_t)blockIdx.x * CH + c) * DD + threadIdx.x];
    out[blockIdx.x * DD + threadIdx.x] = __float2bfloat16_rn(a);
}

typedef CUresult (*EncodeFn)(CUtensorMap*, CUtensorMapDataType, cuuint32_t, void*, const cuuint64_t*, const cuuint64_t*, const cuuint32_t*,
                             const cuuint32_t*, CUtensorMapInterleave, CUtensorMapSwizzle, CUtensorMapL2promotion, CUtensorMapFloatOOBfill);
static CUtensorMap make_map(EncodeFn fn, void* p, uint64_t cols, uint64_t rows, uint32_t bc, uint32_t br, CUtensorMapSwizzle sw) {
    CUtensorMap m;
    cuuint64_t gd[2] = {cols, rows}, gs[1] = {cols * 2};
    cuuint32_t bx[2] = {bc, br}, es[2] = {1, 1};
    fn(&m, CU_TENSOR_MAP_DATA_TYPE_BFLOAT16, 2, p, gd, gs, bx, es, CU_TENSOR_MAP_INTERLEAVE_NONE, sw, CU_TENSOR_MAP_L2_PROMOTION_NONE,
       CU_TENSOR_MAP_FLOAT_OOB_FILL_NONE);
    return m;
}

template <int NPC, int NLATE, int BOFF, int ZT, int HOLD, int TD>
static void launch(void* const* d_in, void* d_out, Scratch* sc, cudaStream_t stream) {
    static EncodeFn fn = nullptr;
    static int sms = 0;
    auto kern = linformer_kernel<NPC, NLATE, BOFF, ZT, HOLD, TD>;
    constexpr int smem = Plan<NPC, NLATE>::SMEM;
    if (!sms) {
        int dev = 0;
        void* f = nullptr;
        cudaDriverEntryPointQueryResult qr;
        cudaGetDevice(&dev);
        cudaDeviceGetAttribute(&sms, cudaDevAttrMultiProcessorCount, dev);
        cudaGetDriverEntryPoint("cuTensorMapEncodeTiled", &f, cudaEnableDefault, &qr);
        fn = (EncodeFn)f;
        cudaFuncSetAttribute(kern, cudaFuncAttributeMaxDynamicSharedMemorySize, smem);
    }
    const __nv_bfloat16 *q = (const __nv_bfloat16*)d_in[0], *k = (const __nv_bfloat16*)d_in[1], *v = (const __nv_bfloat16*)d_in[2];
    const __nv_bfloat16 *e = (const __nv_bfloat16*)d_in[3], *f = (const __nv_bfloat16*)d_in[4];
    if (sms < 2 * BH || !fn) {
        fb_scores<<<NK, 256, 0, stream>>>(q, k, e, sc);
        fb_softmax<<<BH, RR, 0, stream>>>(sc);
        fb_values<<<NK, 256, 0, stream>>>(v, f, sc);
        fb_final<<<BH, DD, 0, stream>>>(sc, (__nv_bfloat16*)d_out);
        return;
    }
    const CUtensorMap me = make_map(fn, d_in[3], NN, RR, 64, 64, CU_TENSOR_MAP_SWIZZLE_128B);
    const CUtensorMap mf = make_map(fn, d_in[4], NN, RR, 64, 64, CU_TENSOR_MAP_SWIZZLE_128B);
    const CUtensorMap mv = make_map(fn, d_in[2], DD, (uint64_t)BH * NN, 128, 128, CU_TENSOR_MAP_SWIZZLE_NONE);
    const CUtensorMap mc = make_map(fn, d_in[2], DD, (uint64_t)BH * NN, 128, 64, CU_TENSOR_MAP_SWIZZLE_NONE);
    kern<<<sms, THREADS, smem, stream>>>(me, mf, mv, mc, (const char*)q, (const char*)k, (const char*)v, (__nv_bfloat16*)d_out, sc);
}

}

extern "C" void kernel_launch(void* const* d_in, const int* in_sizes, int n_in, void* d_out, int out_size) {
    static lf::Scratch* sc = nullptr;
    if (!sc) cudaGetSymbolAddress((void**)&sc, lf::g_scratch);
    lf::launch<4, 3, 700, 1200, 800, 500>(d_in, d_out, sc, cudaStreamPerThread);
}
```
